```python
import torch

def _softmax(x, axis=-1):
    return torch.softmax(x, dim=axis)
def _gelu(x):
    return torch.nn.functional.gelu(x, approximate="tanh")
def _silu(x):
    return torch.nn.functional.silu(x)
def _sigmoid(x):
    return torch.sigmoid(x)
def _layernorm(x, axis=-1, eps=1e-5):
    m = x.mean(dim=axis, keepdim=True)
    v = x.var(dim=axis, keepdim=True, unbiased=False)
    return (x - m) / torch.sqrt(v + eps)
def _scatter_add(tgt, idx, src, axis=0):
    return tgt.clone().index_add_(axis, idx, src)
def _segment_sum(src, seg, n):
    out = torch.zeros((n,) + src.shape[1:], dtype=src.dtype)
    return out.index_add_(0, seg, src)
def _pad(x, pw):
    flat = tuple(v for pair in reversed(pw) for v in pair)
    return torch.nn.functional.pad(x, flat)

kernel_name = 'standalone__gqa_block_cached__decode'

def setup_inputs():

    _w = (lambda a: (lambda t: t.to(torch.bfloat16) if t.is_floating_point() else t)(torch.as_tensor(a)))
    B, Sq, D = 8, 1, 512
    Hq, Hkv, Sk, Dh = 32, 8, 8192, 128
    assert Hq % Hkv == 0, (Hq, Hkv)
    return {
        "x": _w((lambda *s: torch.randn(*s, dtype=torch.bfloat16) * 0.8)(B, Sq, D)),
        "k_cache": _w((lambda *s: torch.randn(*s, dtype=torch.bfloat16) * 0.8)(B, Hkv, Sk, Dh)),
        "v_cache": _w((lambda *s: torch.randn(*s, dtype=torch.bfloat16) * 0.05)(B, Hkv, Sk, Dh)),
        "wq": _w((lambda *s: torch.randn(*s, dtype=torch.bfloat16) * 0.8)(D, Hq * Dh) * (D ** -0.5)),
        "wo": _w((lambda *s: torch.randn(*s, dtype=torch.bfloat16) * 0.05)(Hq * Dh, D) * ((Hq * Dh) ** -0.5)),
    }

def reference(x, k_cache, v_cache, wq, wo):
    B, Sq, D = x.shape
    Hq, Dh = 32, 128
    Hkv = k_cache.shape[1]
    rep = Hq // Hkv
    q = (lambda x, *d: x.permute(*d))((x @ wq).reshape(B, Sq, Hq, Dh), 0, 2, 1, 3)
    k = (lambda x, n, axis: torch.repeat_interleave(x, n, dim=axis))(k_cache, rep, axis=1)
    v = (lambda x, n, axis: torch.repeat_interleave(x, n, dim=axis))(v_cache, rep, axis=1)
    scores = torch.einsum("bhqd,bhkd->bhqk", q, k) * (Dh ** -0.5)
    p = _softmax(scores, axis=-1)
    o = torch.einsum("bhqk,bhkd->bhqd", p, v)
    return (lambda x, *d: x.permute(*d))(o, 0, 2, 1, 3).reshape(B, Sq, Hq * Dh) @ wo
```

```cpp
#include <cuda_runtime.h>
#include <cuda_bf16.h>
#include <cuda.h>
#include <stdint.h>

namespace {

constexpr int B_ = 8, D_ = 512, HQ_ = 32, HKV_ = 8, SK_ = 8192, DH_ = 128;
constexpr int NQ_ = HQ_ * DH_;
constexpr int NPAIR = B_ * HKV_;
constexpr int SPLITS = 2;
constexpr int ATT_CTAS = NPAIR * SPLITS;
constexpr int KEYS_CTA = SK_ / SPLITS;
constexpr int KEYS_STAGE = 64;
constexpr int NITER = KEYS_CTA / KEYS_STAGE;
constexpr int STAGE_BYTES = KEYS_STAGE * DH_ * 2 * 2;
constexpr int NSTAGES = 6;
constexpr int NCW = 4;
constexpr int ATT_THREADS = (NCW + 1) * 32;

__device__ __nv_bfloat16 g_q[B_ * NQ_];
__device__ float g_po[ATT_CTAS * 4 * DH_];
__device__ float g_pm[ATT_CTAS * 4];
__device__ float g_pl[ATT_CTAS * 4];
__device__ __nv_bfloat16 g_o[B_ * NQ_];

__device__ __forceinline__ uint32_t smem_u32(const void* p) { return (uint32_t)__cvta_generic_to_shared(p); }
__device__ __forceinline__ void mbar_init(uint32_t bar, uint32_t cnt) {
    asm volatile("mbarrier.init.shared::cta.b64 [%0], %1;" ::"r"(bar), "r"(cnt) : "memory");
}
__device__ __forceinline__ void mbar_expect_tx(uint32_t bar, uint32_t bytes) {
    asm volatile("mbarrier.arrive.expect_tx.shared::cta.b64 _, [%0], %1;" ::"r"(bar), "r"(bytes) : "memory");
}
__device__ __forceinline__ void mbar_arrive(uint32_t bar) {
    asm volatile("mbarrier.arrive.shared::cta.b64 _, [%0];" ::"r"(bar) : "memory");
}
__device__ __forceinline__ void mbar_wait(uint32_t bar, uint32_t parity) {
    asm volatile(
        "{\n"
        ".reg .pred P1;\n"
        "WAIT_LOOP:\n"
        "mbarrier.try_wait.parity.shared::cta.b64 P1, [%0], %1;\n"
        "@P1 bra WAIT_DONE;\n"
        "bra WAIT_LOOP;\n"
        "WAIT_DONE:\n"
        "}\n" ::"r"(bar), "r"(parity) : "memory");
}
__device__ __forceinline__ void tma_load_2d(uint32_t dst, const void* tmap, int c0, int c1, uint32_t bar) {
    asm volatile(
        "cp.async.bulk.tensor.2d.shared::cluster.global.mbarrier::complete_tx::bytes [%0], [%1, {%3, %4}], [%2];"
        ::"r"(dst), "l"(tmap), "r"(bar), "r"(c0), "r"(c1) : "memory");
}
__device__ __forceinline__ void ldsm_x4(uint32_t& r0, uint32_t& r1, uint32_t& r2, uint32_t& r3, uint32_t addr) {
    asm volatile("ldmatrix.sync.aligned.m8n8.x4.shared.b16 {%0,%1,%2,%3}, [%4];"
                 : "=r"(r0), "=r"(r1), "=r"(r2), "=r"(r3) : "r"(addr) : "memory");
}
__device__ __forceinline__ void ldsm_x4_t(uint32_t& r0, uint32_t& r1, uint32_t& r2, uint32_t& r3, uint32_t addr) {
    asm volatile("ldmatrix.sync.aligned.m8n8.x4.trans.shared.b16 {%0,%1,%2,%3}, [%4];"
                 : "=r"(r0), "=r"(r1), "=r"(r2), "=r"(r3) : "r"(addr) : "memory");
}
__device__ __forceinline__ void mma_bf16(float (&d)[4], uint32_t a0, uint32_t a2, uint32_t b0, uint32_t b1) {
    asm volatile(
        "mma.sync.aligned.m16n8k16.row.col.f32.bf16.bf16.f32 {%0,%1,%2,%3}, {%4,%5,%6,%7}, {%8,%9}, {%0,%1,%2,%3};"
        : "+f"(d[0]), "+f"(d[1]), "+f"(d[2]), "+f"(d[3])
        : "r"(a0), "r"(0u), "r"(a2), "r"(0u), "r"(b0), "r"(b1));
}
__device__ __forceinline__ uint32_t pack_bf16(float lo, float hi) {
    __nv_bfloat162 v = __floats2bfloat162_rn(lo, hi);
    return *reinterpret_cast<uint32_t*>(&v);
}
__device__ __forceinline__ float bf16lo(uint32_t v) { return __uint_as_float(v << 16); }
__device__ __forceinline__ float bf16hi(uint32_t v) { return __uint_as_float(v & 0xffff0000u); }

__global__ void __launch_bounds__(256) qproj_kernel(const __nv_bfloat16* __restrict__ x,
                                                    const __nv_bfloat16* __restrict__ wq) {
    __shared__ float xs[D_][B_];
    __shared__ float red[8][B_][32];
    const int tid = threadIdx.x, lane = tid & 31, warp = tid >> 5;
    for (int i = tid; i < B_ * D_; i += 256) {
        int b = i / D_, k = i % D_;
        xs[k][b] = __bfloat162float(x[i]);
    }
    __syncthreads();
    const int cq = tid & 3, rg = tid >> 2;
    const int col0 = blockIdx.x * 32 + cq * 8;
    float acc[B_][8];
#pragma unroll
    for (int b = 0; b < B_; b++)
#pragma unroll
        for (int c = 0; c < 8; c++) acc[b][c] = 0.f;
    uint4 w[8];
#pragma unroll
    for (int i = 0; i < 8; i++) {
        int k = rg + 64 * i;
        w[i] = *reinterpret_cast<const uint4*>(wq + (size_t)k * NQ_ + col0);
    }
#pragma unroll
    for (int i = 0; i < 8; i++) {
        int k = rg + 64 * i;
        float4 xa = *reinterpret_cast<const float4*>(&xs[k][0]);
        float4 xb = *reinterpret_cast<const float4*>(&xs[k][4]);
        float xv[8] = {xa.x, xa.y, xa.z, xa.w, xb.x, xb.y, xb.z, xb.w};
        float wf[8] = {bf16lo(w[i].x), bf16hi(w[i].x), bf16lo(w[i].y), bf16hi(w[i].y),
                       bf16lo(w[i].z), bf16hi(w[i].z), bf16lo(w[i].w), bf16hi(w[i].w)};
#pragma unroll
        for (int b = 0; b < B_; b++)
#pragma unroll
            for (int c = 0; c < 8; c++) acc[b][c] = fmaf(xv[b], wf[c], acc[b][c]);
    }
    {
        const bool hi = (lane & 16) != 0;
#pragma unroll
        for (int b = 0; b < 4; b++)
#pragma unroll
            for (int c = 0; c < 8; c++) {
                float send = hi ? acc[b][c] : acc[b + 4][c];
                float keep = hi ? acc[b + 4][c] : acc[b][c];
                acc[b][c] = keep + __shfl_xor_sync(0xffffffffu, send, 16);
            }
    }
    {
        const bool hi = (lane & 8) != 0;
#pragma unroll
        for (int b = 0; b < 2; b++)
#pragma unroll
            for (int c = 0; c < 8; c++) {
                float send = hi ? acc[b][c] : acc[b + 2][c];
                float keep = hi ? acc[b + 2][c] : acc[b][c];
                acc[b][c] = keep + __shfl_xor_sync(0xffffffffu, send, 8);
            }
    }
    {
        const bool hi = (lane & 4) != 0;
#pragma unroll
        for (int c = 0; c < 8; c++) {
            float send = hi ? acc[0][c] : acc[1][c];
            float keep = hi ? acc[1][c] : acc[0][c];
            acc[0][c] = keep + __shfl_xor_sync(0xffffffffu, send, 4);
        }
    }
    {
        const int b = ((lane >> 4) & 1) * 4 + ((lane >> 3) & 1) * 2 + ((lane >> 2) & 1);
#pragma unroll
        for (int c = 0; c < 8; c++) red[warp][b][cq * 8 + c] = acc[0][c];
    }
    __syncthreads();
    {
        const int b = tid >> 5, col = tid & 31;
        float s = 0.f;
#pragma unroll
        for (int w2 = 0; w2 < 8; w2++) s += red[w2][b][col];
        g_q[b * NQ_ + blockIdx.x * 32 + col] = __float2bfloat16_rn(s);
    }
}

__global__ void __launch_bounds__(ATT_THREADS, 1)
attn_kernel(const __grid_constant__ CUtensorMap tmK, const __grid_constant__ CUtensorMap tmV) {
    extern __shared__ uint8_t smem_raw[];
    uint8_t* smem = reinterpret_cast<uint8_t*>((reinterpret_cast<uintptr_t>(smem_raw) + 1023) & ~uintptr_t(1023));
    uint8_t* ring = smem;
    float* comb_o = reinterpret_cast<float*>(smem + NSTAGES * STAGE_BYTES);
    float* comb_m = comb_o + NCW * 4 * DH_;
    float* comb_l = comb_m + NCW * 4;
    uint64_t* bars = reinterpret_cast<uint64_t*>(comb_l + NCW * 4);

    const int tid = threadIdx.x, lane = tid & 31, warp = tid >> 5;
    const int pair = blockIdx.x / SPLITS, half = blockIdx.x % SPLITS;
    const int b = pair / HKV_, hkv = pair % HKV_;
    const uint32_t full0 = smem_u32(bars), empty0 = smem_u32(bars + NSTAGES);

    if (tid == 0) {
        for (int s = 0; s < NSTAGES; s++) {
            mbar_init(full0 + 8 * s, 1);
            mbar_init(empty0 + 8 * s, NCW);
        }
        asm volatile("fence.mbarrier_init.release.cluster;" ::: "memory");
    }
    __syncthreads();

    if (warp == NCW) {
        if (lane == 0) {
            const int row0 = pair * SK_ + half * KEYS_CTA;
            const uint32_t ring_a = smem_u32(ring);
            for (int it = 0; it < NITER; it++) {
                const int s = it % NSTAGES;
                const uint32_t ph = (it / NSTAGES) & 1;
                mbar_wait(empty0 + 8 * s, ph ^ 1);
                mbar_expect_tx(full0 + 8 * s, STAGE_BYTES);
                const uint32_t dst = ring_a + s * STAGE_BYTES;
                const int r = row0 + it * KEYS_STAGE;
                tma_load_2d(dst, &tmK, 0, r, full0 + 8 * s);
                tma_load_2d(dst + 8192, &tmK, 64, r, full0 + 8 * s);
                tma_load_2d(dst + 16384, &tmV, 0, r, full0 + 8 * s);
                tma_load_2d(dst + 24576, &tmV, 64, r, full0 + 8 * s);
            }
        }
    } else {
        const int g = lane >> 2, t = lane & 3;
        uint32_t qa[8][2];
        {
            const __nv_bfloat16* qp = g_q + b * NQ_ + (hkv * 4 + (g & 3)) * DH_ + 2 * t;
#pragma unroll
            for (int ks = 0; ks < 8; ks++) {
                uint32_t v0 = *reinterpret_cast<const uint32_t*>(qp + 16 * ks);
                uint32_t v1 = *reinterpret_cast<const uint32_t*>(qp + 16 * ks + 8);
                qa[ks][0] = (g < 4) ? v0 : 0u;
                qa[ks][1] = (g < 4) ? v1 : 0u;
            }
        }
        const float cs = 0.08838834764831845f * 1.4426950408889634f;
        float oacc[16][4];
#pragma unroll
        for (int i = 0; i < 16; i++) { oacc[i][0] = oacc[i][1] = oacc[i][2] = oacc[i][3] = 0.f; }
        float m_run = -INFINITY, l_run = 0.f;

        const uint32_t ring_a = smem_u32(ring);
        const uint32_t koff = (16 * warp + (lane & 7)) * 128 + ((((lane >> 3) ^ (lane & 7))) << 4);
        const uint32_t voff = 16384 + (16 * warp + ((lane >> 3) & 1) * 8 + (lane & 7)) * 128 +
                              ((((lane >> 4) ^ (lane & 7))) << 4);

        for (int it = 0; it < NITER; it++) {
            const int s = it % NSTAGES;
            const uint32_t ph = (it / NSTAGES) & 1;
            mbar_wait(full0 + 8 * s, ph);
            const uint32_t sb = ring_a + s * STAGE_BYTES;
            float sacc[2][4];
#pragma unroll
            for (int j = 0; j < 2; j++) { sacc[j][0] = sacc[j][1] = sacc[j][2] = sacc[j][3] = 0.f; }
#pragma unroll
            for (int cq = 0; cq < 4; cq++) {
#pragma unroll
                for (int j = 0; j < 2; j++) {
                    uint32_t r0, r1, r2, r3;
                    uint32_t a = sb + ((koff + j * 1024 + (cq >> 1) * 8192) ^ ((cq & 1) << 6));
                    ldsm_x4(r0, r1, r2, r3, a);
                    mma_bf16(sacc[j], qa[2 * cq][0], qa[2 * cq][1], r0, r1);
                    mma_bf16(sacc[j], qa[2 * cq + 1][0], qa[2 * cq + 1][1], r2, r3);
                }
            }
            float mx = fmaxf(fmaxf(sacc[0][0], sacc[0][1]), fmaxf(sacc[1][0], sacc[1][1]));
            mx = fmaxf(mx, __shfl_xor_sync(0xffffffffu, mx, 1));
            mx = fmaxf(mx, __shfl_xor_sync(0xffffffffu, mx, 2));
            const float m_new = fmaxf(m_run, mx);
            if (__any_sync(0xffffffffu, m_new > m_run)) {
                const float alpha = exp2f((m_run - m_new) * cs);
                l_run *= alpha;
#pragma unroll
                for (int i = 0; i < 16; i++) { oacc[i][0] *= alpha; oacc[i][1] *= alpha; }
                m_run = m_new;
            }
            const float mc = m_run * cs;
            const float p0 = exp2f(fmaf(sacc[0][0], cs, -mc));
            const float p1 = exp2f(fmaf(sacc[0][1], cs, -mc));
            const float p2 = exp2f(fmaf(sacc[1][0], cs, -mc));
            const float p3 = exp2f(fmaf(sacc[1][1], cs, -mc));
            l_run += (p0 + p1) + (p2 + p3);
            const uint32_t pa0 = pack_bf16(p0, p1), pa2 = pack_bf16(p2, p3);
#pragma unroll
            for (int nq = 0; nq < 8; nq++) {
                uint32_t r0, r1, r2, r3;
                uint32_t a = sb + ((voff + (nq >> 2) * 8192) ^ ((nq & 3) << 5));
                ldsm_x4_t(r0, r1, r2, r3, a);
                mma_bf16(oacc[2 * nq], pa0, pa2, r0, r1);
                mma_bf16(oacc[2 * nq + 1], pa0, pa2, r2, r3);
            }
            __syncwarp();
            if (lane == 0) mbar_arrive(empty0 + 8 * s);
        }
        l_run += __shfl_xor_sync(0xffffffffu, l_run, 1);
        l_run += __shfl_xor_sync(0xffffffffu, l_run, 2);
        if (g < 4) {
            float* dst = comb_o + (warp * 4 + g) * DH_ + 2 * t;
#pragma unroll
            for (int i = 0; i < 16; i++) *reinterpret_cast<float2*>(dst + 8 * i) = make_float2(oacc[i][0], oacc[i][1]);
            if (t == 0) { comb_m[warp * 4 + g] = m_run; comb_l[warp * 4 + g] = l_run; }
        }
        asm volatile("bar.sync 1, %0;" ::"n"(NCW * 32) : "memory");
        {
            const int d = tid;
#pragma unroll
            for (int h = 0; h < 4; h++) {
                float M = -INFINITY;
#pragma unroll
                for (int w2 = 0; w2 < NCW; w2++) M = fmaxf(M, comb_m[w2 * 4 + h]);
                float o = 0.f, L = 0.f;
#pragma unroll
                for (int w2 = 0; w2 < NCW; w2++) {
                    const float sc = exp2f((comb_m[w2 * 4 + h] - M) * cs);
                    o = fmaf(sc, comb_o[(w2 * 4 + h) * DH_ + d], o);
                    L = fmaf(sc, comb_l[w2 * 4 + h], L);
                }
                g_po[(blockIdx.x * 4 + h) * DH_ + d] = o;
                if (d == 0) { g_pm[blockIdx.x * 4 + h] = M; g_pl[blockIdx.x * 4 + h] = L; }
            }
        }
    }
}

__global__ void __launch_bounds__(128) combine_kernel() {
    const int bh = blockIdx.x;
    const int b = bh / HQ_, hq = bh % HQ_;
    const int pair = b * HKV_ + hq / 4, h = hq % 4;
    const int d = threadIdx.x;
    const float cs = 0.08838834764831845f * 1.4426950408889634f;
    float M = -INFINITY;
#pragma unroll
    for (int s = 0; s < SPLITS; s++) M = fmaxf(M, g_pm[(pair * SPLITS + s) * 4 + h]);
    float o = 0.f, L = 0.f;
#pragma unroll
    for (int s = 0; s < SPLITS; s++) {
        const int c = pair * SPLITS + s;
        const float sc = exp2f((g_pm[c * 4 + h] - M) * cs);
        o = fmaf(sc, g_po[(c * 4 + h) * DH_ + d], o);
        L = fmaf(sc, g_pl[c * 4 + h], L);
    }
    g_o[b * NQ_ + hq * DH_ + d] = __float2bfloat16_rn(o / L);
}

__global__ void __launch_bounds__(256) oproj_kernel(const __nv_bfloat16* __restrict__ wo,
                                                    __nv_bfloat16* __restrict__ out) {
    __shared__ float red[8][B_][4];
    const int tid = threadIdx.x, lane = tid & 31, warp = tid >> 5;
    const int col0 = blockIdx.x * 4;
    float acc[B_][4];
#pragma unroll
    for (int b = 0; b < B_; b++)
#pragma unroll
        for (int c = 0; c < 4; c++) acc[b][c] = 0.f;
    for (int k = tid; k < NQ_; k += 256) {
        uint2 w = *reinterpret_cast<const uint2*>(wo + (size_t)k * D_ + col0);
        float wf[4] = {bf16lo(w.x), bf16hi(w.x), bf16lo(w.y), bf16hi(w.y)};
#pragma unroll
        for (int b = 0; b < B_; b++) {
            float ov = __bfloat162float(g_o[b * NQ_ + k]);
#pragma unroll
            for (int c = 0; c < 4; c++) acc[b][c] = fmaf(ov, wf[c], acc[b][c]);
        }
    }
#pragma unroll
    for (int b = 0; b < B_; b++)
#pragma unroll
        for (int c = 0; c < 4; c++) {
            float v = acc[b][c];
#pragma unroll
            for (int o = 16; o > 0; o >>= 1) v += __shfl_xor_sync(0xffffffffu, v, o);
            if (lane == 0) red[warp][b][c] = v;
        }
    __syncthreads();
    if (tid < 32) {
        const int b = tid >> 2, c = tid & 3;
        float s = 0.f;
#pragma unroll
        for (int w2 = 0; w2 < 8; w2++) s += red[w2][b][c];
        out[b * D_ + col0 + c] = __float2bfloat16_rn(s);
    }
}

typedef CUresult (*PFN_tmapEncode)(CUtensorMap*, CUtensorMapDataType, cuuint32_t, void*, const cuuint64_t*,
                                   const cuuint64_t*, const cuuint32_t*, const cuuint32_t*, CUtensorMapInterleave,
                                   CUtensorMapSwizzle, CUtensorMapL2promotion, CUtensorMapFloatOOBfill);

void make_kv_map(PFN_tmapEncode enc, CUtensorMap* m, const void* ptr) {
    cuuint64_t gdim[2] = {(cuuint64_t)DH_, (cuuint64_t)B_ * HKV_ * SK_};
    cuuint64_t gstr[1] = {(cuuint64_t)DH_ * 2};
    cuuint32_t box[2] = {64, (cuuint32_t)KEYS_STAGE};
    cuuint32_t estr[2] = {1, 1};
    enc(m, CU_TENSOR_MAP_DATA_TYPE_BFLOAT16, 2, const_cast<void*>(ptr), gdim, gstr, box, estr,
        CU_TENSOR_MAP_INTERLEAVE_NONE, CU_TENSOR_MAP_SWIZZLE_128B, CU_TENSOR_MAP_L2_PROMOTION_L2_256B,
        CU_TENSOR_MAP_FLOAT_OOB_FILL_NONE);
}

}

extern "C" void kernel_launch(void* const* d_in, const int* in_sizes, int n_in, void* d_out, int out_size) {
    const __nv_bfloat16* x = (const __nv_bfloat16*)d_in[0];
    const __nv_bfloat16* kc = (const __nv_bfloat16*)d_in[1];
    const __nv_bfloat16* vc = (const __nv_bfloat16*)d_in[2];
    const __nv_bfloat16* wq = (const __nv_bfloat16*)d_in[3];
    const __nv_bfloat16* wo = (const __nv_bfloat16*)d_in[4];
    __nv_bfloat16* out = (__nv_bfloat16*)d_out;

    static PFN_tmapEncode enc = nullptr;
    if (!enc) {
        void* fn = nullptr;
        cudaDriverEntryPointQueryResult qres;
        cudaGetDriverEntryPoint("cuTensorMapEncodeTiled", &fn, cudaEnableDefault, &qres);
        enc = (PFN_tmapEncode)fn;
    }
    CUtensorMap tmK, tmV;
    make_kv_map(enc, &tmK, kc);
    make_kv_map(enc, &tmV, vc);

    constexpr int ATT_SMEM = NSTAGES * STAGE_BYTES + NCW * 4 * DH_ * 4 + NCW * 4 * 4 * 2 + 2 * NSTAGES * 8 + 1024;
    static bool attr_set = false;
    if (!attr_set) {
        cudaFuncSetAttribute(attn_kernel, cudaFuncAttributeMaxDynamicSharedMemorySize, ATT_SMEM);
        attr_set = true;
    }

    qproj_kernel<<<128, 256>>>(x, wq);
    attn_kernel<<<ATT_CTAS, ATT_THREADS, ATT_SMEM>>>(tmK, tmV);
    combine_kernel<<<B_ * HQ_, 128>>>();
    oproj_kernel<<<128, 256>>>(wo, out);
}
```

```cpp
#include <cuda_runtime.h>
#include <cuda_bf16.h>
#include <cuda.h>
#include <stdint.h>

namespace {

constexpr int B_ = 8, D_ = 512, HQ_ = 32, HKV_ = 8, SK_ = 8192, DH_ = 128;
constexpr int NQ_ = HQ_ * DH_;
constexpr int NPAIR = B_ * HKV_;
constexpr int NCTA = NPAIR * 2;
constexpr int KEYS_CTA = SK_ / 2;
constexpr int KEYS_STAGE = 64;
constexpr int NITER = KEYS_CTA / KEYS_STAGE;
constexpr int STAGE_BYTES = KEYS_STAGE * DH_ * 2 * 2;
constexpr int NSTAGES = 5;
constexpr int NCW = 4;
constexpr int NTHREADS = (NCW + 1) * 32;
constexpr int AUX_BYTES = 32768;

constexpr int OFF_RING = 0;
constexpr int OFF_AUX = OFF_RING + NSTAGES * STAGE_BYTES;
constexpr int OFF_COMB = OFF_AUX + AUX_BYTES;
constexpr int OFF_COMBM = OFF_COMB + NCW * 4 * DH_ * 4;
constexpr int OFF_COMBL = OFF_COMBM + NCW * 4 * 4;
constexpr int OFF_RECVO = OFF_COMBL + NCW * 4 * 4;
constexpr int OFF_RECVML = OFF_RECVO + 2 * DH_ * 4;
constexpr int OFF_RECVOUT = OFF_RECVML + 16;
constexpr int OFF_BARS = OFF_RECVOUT + 64 * 4;
constexpr int SMEM_USED = OFF_BARS + (2 * NSTAGES + 4) * 8;
constexpr int SMEM_BYTES = SMEM_USED + 1024;

constexpr uint32_t RECVO_BYTES = 2 * DH_ * 4 + 16;
constexpr uint32_t RECVOUT_BYTES = 64 * 4;
constexpr int SPIN_LIMIT = 1 << 22;
#define PRE_STAGES 1
#define WINDOW 2

__device__ unsigned long long g_q2[B_ * NQ_ / 2];
__device__ unsigned long long g_o2[B_ * NQ_ / 2];
__device__ unsigned int g_epoch;
__device__ unsigned int g_exitcnt;
#define TL(i)

__device__ __forceinline__ uint32_t smem_u32(const void* p) { return (uint32_t)__cvta_generic_to_shared(p); }
__device__ __forceinline__ void mbar_init(uint32_t bar, uint32_t cnt) {
    asm volatile("mbarrier.init.shared::cta.b64 [%0], %1;" ::"r"(bar), "r"(cnt) : "memory");
}
__device__ __forceinline__ void mbar_expect_tx(uint32_t bar, uint32_t bytes) {
    asm volatile("mbarrier.arrive.expect_tx.shared::cta.b64 _, [%0], %1;" ::"r"(bar), "r"(bytes) : "memory");
}
__device__ __forceinline__ void mbar_arrive(uint32_t bar) {
    asm volatile("mbarrier.arrive.shared::cta.b64 _, [%0];" ::"r"(bar) : "memory");
}
__device__ __forceinline__ void mbar_wait(uint32_t bar, uint32_t parity) {
    asm volatile(
        "{\n"
        ".reg .pred P1;\n"
        "WAIT_LOOP:\n"
        "mbarrier.try_wait.parity.shared::cta.b64 P1, [%0], %1;\n"
        "@P1 bra WAIT_DONE;\n"
        "bra WAIT_LOOP;\n"
        "WAIT_DONE:\n"
        "}\n" ::"r"(bar), "r"(parity) : "memory");
}
__device__ __forceinline__ void mbar_wait_cluster(uint32_t bar, uint32_t parity) {
    asm volatile(
        "{\n"
        ".reg .pred P1;\n"
        "WAIT_LOOP:\n"
        "mbarrier.try_wait.parity.acquire.cluster.shared::cta.b64 P1, [%0], %1;\n"
        "@P1 bra WAIT_DONE;\n"
        "bra WAIT_LOOP;\n"
        "WAIT_DONE:\n"
        "}\n" ::"r"(bar), "r"(parity) : "memory");
}
__device__ __forceinline__ void tma_load_2d(uint32_t dst, const void* tmap, int c0, int c1, uint32_t bar) {
    asm volatile(
        "cp.async.bulk.tensor.2d.shared::cluster.global.mbarrier::complete_tx::bytes [%0], [%1, {%3, %4}], [%2];"
        ::"r"(dst), "l"(tmap), "r"(bar), "r"(c0), "r"(c1) : "memory");
}
__device__ __forceinline__ void ldsm_x4(uint32_t& r0, uint32_t& r1, uint32_t& r2, uint32_t& r3, uint32_t addr) {
    asm volatile("ldmatrix.sync.aligned.m8n8.x4.shared.b16 {%0,%1,%2,%3}, [%4];"
                 : "=r"(r0), "=r"(r1), "=r"(r2), "=r"(r3) : "r"(addr) : "memory");
}
__device__ __forceinline__ void ldsm_x4_t(uint32_t& r0, uint32_t& r1, uint32_t& r2, uint32_t& r3, uint32_t addr) {
    asm volatile("ldmatrix.sync.aligned.m8n8.x4.trans.shared.b16 {%0,%1,%2,%3}, [%4];"
                 : "=r"(r0), "=r"(r1), "=r"(r2), "=r"(r3) : "r"(addr) : "memory");
}
__device__ __forceinline__ void mma_bf16(float (&d)[4], uint32_t a0, uint32_t a2, uint32_t b0, uint32_t b1) {
    asm volatile(
        "mma.sync.aligned.m16n8k16.row.col.f32.bf16.bf16.f32 {%0,%1,%2,%3}, {%4,%5,%6,%7}, {%8,%9}, {%0,%1,%2,%3};"
        : "+f"(d[0]), "+f"(d[1]), "+f"(d[2]), "+f"(d[3])
        : "r"(a0), "r"(0u), "r"(a2), "r"(0u), "r"(b0), "r"(b1));
}
__device__ __forceinline__ uint32_t pack_bf16(float lo, float hi) {
    __nv_bfloat162 v = __floats2bfloat162_rn(lo, hi);
    return *reinterpret_cast<uint32_t*>(&v);
}
__device__ __forceinline__ uint32_t mapa_u32(uint32_t addr, uint32_t rank) {
    uint32_t r;
    asm volatile("mapa.shared::cluster.u32 %0, %1, %2;" : "=r"(r) : "r"(addr), "r"(rank));
    return r;
}
__device__ __forceinline__ void st_async_f32(uint32_t addr, float v, uint32_t bar) {
    asm volatile("st.async.weak.shared::cluster.mbarrier::complete_tx::bytes.f32 [%0], %1, [%2];"
                 ::"r"(addr), "f"(v), "r"(bar) : "memory");
}
__device__ __forceinline__ ulonglong2 ld_relaxed_v2(const unsigned long long* p) {
    ulonglong2 v;
    asm volatile("ld.relaxed.gpu.global.v2.u64 {%0,%1}, [%2];" : "=l"(v.x), "=l"(v.y) : "l"(p) : "memory");
    return v;
}
__device__ __forceinline__ void st_relaxed_u64(unsigned long long* p, unsigned long long v) {
    asm volatile("st.relaxed.gpu.global.u64 [%0], %1;" ::"l"(p), "l"(v) : "memory");
}
__device__ __forceinline__ unsigned int ld_relaxed_u32(const unsigned int* p) {
    unsigned int v;
    asm volatile("ld.relaxed.gpu.global.u32 %0, [%1];" : "=r"(v) : "l"(p) : "memory");
    return v;
}
__device__ __forceinline__ void consumer_sync() { asm volatile("bar.sync 1, %0;" ::"n"(NCW * 32) : "memory"); }
__device__ __forceinline__ int pos32(int kk) {
    return ((kk >> 1) & 3) * 8 + (kk >> 4) * 4 + ((kk >> 3) & 1) * 2 + (kk & 1);
}

__global__ void __cluster_dims__(2, 1, 1) __launch_bounds__(NTHREADS, 1)
fused_kernel(const __grid_constant__ CUtensorMap tmK, const __grid_constant__ CUtensorMap tmV,
             const __grid_constant__ CUtensorMap tmWq, const __grid_constant__ CUtensorMap tmWo,
             const __nv_bfloat16* __restrict__ x, __nv_bfloat16* __restrict__ out) {
    extern __shared__ uint8_t smem_raw[];
    uint8_t* smem = reinterpret_cast<uint8_t*>((reinterpret_cast<uintptr_t>(smem_raw) + 1023) & ~uintptr_t(1023));
    const uint32_t sbase = smem_u32(smem);
    const uint32_t full0 = sbase + OFF_BARS, empty0 = full0 + 8 * NSTAGES;
    const uint32_t bar_wq = empty0 + 8 * NSTAGES, bar_wo = bar_wq + 8, bar_recvo = bar_wq + 16, bar_recvout = bar_wq + 24;

    const int tid = threadIdx.x, lane = tid & 31, warp = tid >> 5;
    const int cta = blockIdx.x;
    const int pair = cta >> 1, rank = cta & 1;
    const int b = pair / HKV_, hkv = pair % HKV_;

    TL(0);
    if (tid == 0) {
        for (int s = 0; s < NSTAGES; s++) {
            mbar_init(full0 + 8 * s, 1);
            mbar_init(empty0 + 8 * s, NCW);
        }
        mbar_init(bar_wq, 1);
        mbar_init(bar_wo, 1);
        mbar_init(bar_recvo, 1);
        mbar_init(bar_recvout, 1);
        asm volatile("fence.mbarrier_init.release.cluster;" ::: "memory");
        mbar_expect_tx(bar_recvo, RECVO_BYTES);
        mbar_expect_tx(bar_recvout, RECVOUT_BYTES);
    }
    __syncthreads();
    asm volatile("barrier.cluster.arrive.release.aligned;" ::: "memory");

    if (warp == NCW) {
        if (lane == 0) {
            mbar_expect_tx(bar_wq, AUX_BYTES);
            tma_load_2d(sbase + OFF_AUX, &tmWq, cta * 32, 0, bar_wq);
            tma_load_2d(sbase + OFF_AUX + 16384, &tmWq, cta * 32, 256, bar_wq);
            const int row0 = pair * SK_ + rank * KEYS_CTA;
            for (int it = 0; it < NITER; it++) {
                const int s = it % NSTAGES;
                const uint32_t ph = (it / NSTAGES) & 1;
                if (it == PRE_STAGES) mbar_wait(bar_wq, 0);
                mbar_wait(empty0 + 8 * s, ph ^ 1);
                if (it >= WINDOW) {
                    const int j = it - WINDOW;
                    mbar_wait(full0 + 8 * (j % NSTAGES), (j / NSTAGES) & 1);
                }
                mbar_expect_tx(full0 + 8 * s, STAGE_BYTES);
                const uint32_t dst = sbase + OFF_RING + s * STAGE_BYTES;
                const int r = row0 + it * KEYS_STAGE;
                tma_load_2d(dst, &tmK, 0, r, full0 + 8 * s);
                tma_load_2d(dst + 8192, &tmK, 64, r, full0 + 8 * s);
                tma_load_2d(dst + 16384, &tmV, 0, r, full0 + 8 * s);
                tma_load_2d(dst + 24576, &tmV, 64, r, full0 + 8 * s);
            }
            mbar_expect_tx(bar_wo, AUX_BYTES);
#pragma unroll 1
            for (int i = 0; i < 8; i++)
                tma_load_2d(sbase + OFF_AUX + i * 4096, &tmWo, pair * 8, rank * 2048 + i * 256, bar_wo);
        }
        __syncwarp();
        asm volatile("barrier.cluster.wait.acquire.aligned;" ::: "memory");
        return;
    }

    const int g = lane >> 2, t = lane & 3;
    const float cs = 0.08838834764831845f * 1.4426950408889634f;
    float* comb = reinterpret_cast<float*>(smem + OFF_COMB);
    const uint32_t tag = ld_relaxed_u32(&g_epoch) + 1u;
    const unsigned long long tag64 = (unsigned long long)tag << 32;

    {
        uint32_t xa[8][2];
        const __nv_bfloat16* xp = x + g * D_ + warp * 128 + 2 * t;
#pragma unroll
        for (int ks = 0; ks < 8; ks++) {
            xa[ks][0] = __ldg(reinterpret_cast<const uint32_t*>(xp + 16 * ks));
            xa[ks][1] = __ldg(reinterpret_cast<const uint32_t*>(xp + 16 * ks + 8));
        }
        asm volatile("barrier.cluster.wait.acquire.aligned;" ::: "memory");
        float qacc[4][4];
#pragma unroll
        for (int i = 0; i < 4; i++) { qacc[i][0] = qacc[i][1] = qacc[i][2] = qacc[i][3] = 0.f; }
        const uint32_t wbase = sbase + OFF_AUX + (warp * 128 + ((lane >> 3) & 1) * 8 + (lane & 7)) * 64;
        const uint32_t swz = (lane & 7) >> 1;
        mbar_wait(bar_wq, 0);
        TL(1);
#pragma unroll
        for (int ks = 0; ks < 8; ks++) {
#pragma unroll
            for (int cp = 0; cp < 2; cp++) {
                uint32_t r0, r1, r2, r3;
                const uint32_t chunk = 2 * cp + (lane >> 4);
                ldsm_x4_t(r0, r1, r2, r3, wbase + ks * 1024 + ((chunk ^ swz) << 4));
                mma_bf16(qacc[2 * cp], xa[ks][0], xa[ks][1], r0, r1);
                mma_bf16(qacc[2 * cp + 1], xa[ks][0], xa[ks][1], r2, r3);
            }
        }
        float* red = comb + (warp * 8 + g) * 32 + 2 * t;
#pragma unroll
        for (int nt = 0; nt < 4; nt++) *reinterpret_cast<float2*>(red + 8 * nt) = make_float2(qacc[nt][0], qacc[nt][1]);
        consumer_sync();
        {
            const int bb = tid >> 4, col = (tid & 15) * 2;
            float s0 = 0.f, s1 = 0.f;
#pragma unroll
            for (int w2 = 0; w2 < NCW; w2++) {
                float2 v = *reinterpret_cast<const float2*>(comb + (w2 * 8 + bb) * 32 + col);
                s0 += v.x; s1 += v.y;
            }
            TL(12);
            st_relaxed_u64(g_q2 + (bb * NQ_ + cta * 32 + pos32(col)) / 2, tag64 | pack_bf16(s0, s1));
        }
    }

    {
        uint32_t qa[8][2];
        {
            uint32_t pl[16];
#pragma unroll
            for (int i = 0; i < 16; i++) pl[i] = 0u;
            if (g < 4) {
                const unsigned long long* qp = g_q2 + (b * NQ_ + (hkv * 4 + g) * DH_ + 8 * t) / 2;
                for (int it = 0; it < SPIN_LIMIT; it++) {
                    uint32_t bad = 0;
#pragma unroll
                    for (int i = 0; i < 8; i++) {
                        const ulonglong2 w = ld_relaxed_v2(qp + (i >> 1) * 16 + (i & 1) * 2);
                        pl[2 * i] = (uint32_t)w.x;
                        pl[2 * i + 1] = (uint32_t)w.y;
                        bad |= ((uint32_t)(w.x >> 32) ^ tag) | ((uint32_t)(w.y >> 32) ^ tag);
                    }
                    if (bad == 0) break;
                    __nanosleep(40);
                }
            }
            __syncwarp();
            TL(3);
#pragma unroll
            for (int j = 0; j < 4; j++) {
                qa[2 * j][0] = pl[4 * j]; qa[2 * j][1] = pl[4 * j + 1];
                qa[2 * j + 1][0] = pl[4 * j + 2]; qa[2 * j + 1][1] = pl[4 * j + 3];
            }
        }
        float oacc[16][4];
#pragma unroll
        for (int i = 0; i < 16; i++) { oacc[i][0] = oacc[i][1] = oacc[i][2] = oacc[i][3] = 0.f; }
        float m_run = -INFINITY, l_run = 0.f;

        const uint32_t ring_a = sbase + OFF_RING;
        const uint32_t koff = (16 * warp + (lane & 7)) * 128 + ((((lane >> 3) ^ (lane & 7))) << 4);
        const uint32_t voff = 16384 + (16 * warp + ((lane >> 3) & 1) * 8 + (lane & 7)) * 128 +
                              ((((lane >> 4) ^ (lane & 7))) << 4);

        int s = 0;
        uint32_t ph = 0;
        for (int it = 0; it < NITER; it++) {
            mbar_wait(full0 + 8 * s, ph);
            if (it == 0) TL(4);
            if (it == NITER - 1) TL(5);
            const uint32_t sb = ring_a + s * STAGE_BYTES;
            float sacc[2][4];
#pragma unroll
            for (int j = 0; j < 2; j++) { sacc[j][0] = sacc[j][1] = sacc[j][2] = sacc[j][3] = 0.f; }
#pragma unroll
            for (int cq = 0; cq < 4; cq++) {
#pragma unroll
                for (int j = 0; j < 2; j++) {
                    uint32_t r0, r1, r2, r3;
                    uint32_t a = sb + ((koff + j * 1024 + (cq >> 1) * 8192) ^ ((cq & 1) << 6));
                    ldsm_x4(r0, r1, r2, r3, a);
                    mma_bf16(sacc[j], qa[2 * cq][0], qa[2 * cq][1], r0, r1);
                    mma_bf16(sacc[j], qa[2 * cq + 1][0], qa[2 * cq + 1][1], r2, r3);
                }
            }
            float mx = fmaxf(fmaxf(sacc[0][0], sacc[0][1]), fmaxf(sacc[1][0], sacc[1][1]));
            mx = fmaxf(mx, __shfl_xor_sync(0xffffffffu, mx, 1));
            mx = fmaxf(mx, __shfl_xor_sync(0xffffffffu, mx, 2));
            const float m_new = fmaxf(m_run, mx);
            if (__any_sync(0xffffffffu, m_new > m_run)) {
                const float alpha = exp2f((m_run - m_new) * cs);
                l_run *= alpha;
#pragma unroll
                for (int i = 0; i < 16; i++) { oacc[i][0] *= alpha; oacc[i][1] *= alpha; }
                m_run = m_new;
            }
            const float mc = m_run * cs;
            const float p0 = exp2f(fmaf(sacc[0][0], cs, -mc));
            const float p1 = exp2f(fmaf(sacc[0][1], cs, -mc));
            const float p2 = exp2f(fmaf(sacc[1][0], cs, -mc));
            const float p3 = exp2f(fmaf(sacc[1][1], cs, -mc));
            l_run += (p0 + p1) + (p2 + p3);
            const uint32_t pa0 = pack_bf16(p0, p1), pa2 = pack_bf16(p2, p3);
#pragma unroll
            for (int nq = 0; nq < 8; nq++) {
                uint32_t r0, r1, r2, r3;
                uint32_t a = sb + ((voff + (nq >> 2) * 8192) ^ ((nq & 3) << 5));
                ldsm_x4_t(r0, r1, r2, r3, a);
                mma_bf16(oacc[2 * nq], pa0, pa2, r0, r1);
                mma_bf16(oacc[2 * nq + 1], pa0, pa2, r2, r3);
            }
            __syncwarp();
            if (lane == 0) mbar_arrive(empty0 + 8 * s);
            if (++s == NSTAGES) { s = 0; ph ^= 1; }
        }
        l_run += __shfl_xor_sync(0xffffffffu, l_run, 1);
        l_run += __shfl_xor_sync(0xffffffffu, l_run, 2);
        float* comb_m = reinterpret_cast<float*>(smem + OFF_COMBM);
        float* comb_l = reinterpret_cast<float*>(smem + OFF_COMBL);
        if (g < 4) {
            float* dst = comb + (warp * 4 + g) * DH_ + 2 * t;
#pragma unroll
            for (int i = 0; i < 16; i++) *reinterpret_cast<float2*>(dst + 8 * i) = make_float2(oacc[i][0], oacc[i][1]);
            if (t == 0) { comb_m[warp * 4 + g] = m_run; comb_l[warp * 4 + g] = l_run; }
        }
        consumer_sync();
        {
            const int d = tid;
            float Mh[4], Lh[4], Oh[4];
#pragma unroll
            for (int h = 0; h < 4; h++) {
                float M = -INFINITY;
#pragma unroll
                for (int w2 = 0; w2 < NCW; w2++) M = fmaxf(M, comb_m[w2 * 4 + h]);
                float o = 0.f, L = 0.f;
#pragma unroll
                for (int w2 = 0; w2 < NCW; w2++) {
                    const float sc = exp2f((comb_m[w2 * 4 + h] - M) * cs);
                    o = fmaf(sc, comb[(w2 * 4 + h) * DH_ + d], o);
                    L = fmaf(sc, comb_l[w2 * 4 + h], L);
                }
                Mh[h] = M; Lh[h] = L; Oh[h] = o;
            }
            const uint32_t peer = (uint32_t)(rank ^ 1);
            const uint32_t rbar = mapa_u32(bar_recvo, peer);
            const uint32_t ro = mapa_u32(sbase + OFF_RECVO + d * 4, peer);
            const float po0 = rank ? Oh[0] : Oh[2], po1 = rank ? Oh[1] : Oh[3];
            st_async_f32(ro, po0, rbar);
            st_async_f32(ro + DH_ * 4, po1, rbar);
            if (d == 0) {
                const uint32_t rml = mapa_u32(sbase + OFF_RECVML, peer);
                st_async_f32(rml, rank ? Mh[0] : Mh[2], rbar);
                st_async_f32(rml + 4, rank ? Lh[0] : Lh[2], rbar);
                st_async_f32(rml + 8, rank ? Mh[1] : Mh[3], rbar);
                st_async_f32(rml + 12, rank ? Lh[1] : Lh[3], rbar);
            }
            TL(6);
            mbar_wait_cluster(bar_recvo, 0);
            TL(7);
            const float* rvo = reinterpret_cast<const float*>(smem + OFF_RECVO);
            const float* rvml = reinterpret_cast<const float*>(smem + OFF_RECVML);
#pragma unroll
            for (int hh = 0; hh < 2; hh++) {
                const float Mo = rank ? Mh[2 + hh] : Mh[hh];
                const float Lo = rank ? Lh[2 + hh] : Lh[hh];
                const float Oo = rank ? Oh[2 + hh] : Oh[hh];
                const float Mp = rvml[2 * hh], Lp = rvml[2 * hh + 1], Op = rvo[hh * DH_ + d];
                const float M = fmaxf(Mo, Mp);
                const float eo = exp2f((Mo - M) * cs), ep = exp2f((Mp - M) * cs);
                const float o = (eo * Oo + ep * Op) / (eo * Lo + ep * Lp);
                const float o2 = __shfl_down_sync(0xffffffffu, o, 1);
                if ((d & 1) == 0)
                    st_relaxed_u64(g_o2 + (b * NQ_ + (hkv * 4 + rank * 2 + hh) * DH_ + (d & ~31) + pos32(d & 31)) / 2,
                                   tag64 | pack_bf16(o, o2));
            }
            TL(8);
        }
    }

    {
        const unsigned long long* op = g_o2 + (g * NQ_ + rank * 2048 + warp * 512 + 8 * t) / 2;
        uint32_t av[64];
        for (int it = 0; it < SPIN_LIMIT; it++) {
            uint32_t bad = 0;
#pragma unroll
            for (int i = 0; i < 32; i++) {
                const ulonglong2 w = ld_relaxed_v2(op + (i >> 1) * 16 + (i & 1) * 2);
                av[2 * i] = (uint32_t)w.x;
                av[2 * i + 1] = (uint32_t)w.y;
                bad |= ((uint32_t)(w.x >> 32) ^ tag) | ((uint32_t)(w.y >> 32) ^ tag);
            }
            if (bad == 0) break;
            __nanosleep(40);
        }
        __syncwarp();
        TL(9);
        float acc4[4][4];
#pragma unroll
        for (int i = 0; i < 4; i++) { acc4[i][0] = acc4[i][1] = acc4[i][2] = acc4[i][3] = 0.f; }
        mbar_wait(bar_wo, 0);
        TL(10);
        const uint32_t wb = sbase + OFF_AUX + (warp * 512 + lane) * 16;
#pragma unroll
        for (int j = 0; j < 16; j++) {
            uint32_t r0, r1, r2, r3;
            ldsm_x4_t(r0, r1, r2, r3, wb + j * 512);
            mma_bf16(acc4[j & 3], av[4 * j], av[4 * j + 1], r0, r1);
            mma_bf16(acc4[(j + 2) & 3], av[4 * j + 2], av[4 * j + 3], r2, r3);
        }
        float acc[2];
        acc[0] = (acc4[0][0] + acc4[1][0]) + (acc4[2][0] + acc4[3][0]);
        acc[1] = (acc4[0][1] + acc4[1][1]) + (acc4[2][1] + acc4[3][1]);
        consumer_sync();
        *reinterpret_cast<float2*>(comb + (warp * 8 + g) * 8 + 2 * t) = make_float2(acc[0], acc[1]);
        consumer_sync();
        if (tid < 64) {
            float sum = 0.f;
#pragma unroll
            for (int w2 = 0; w2 < NCW; w2++) sum += comb[w2 * 64 + tid];
            if (rank == 1) {
                st_async_f32(mapa_u32(sbase + OFF_RECVOUT + tid * 4, 0u), sum, mapa_u32(bar_recvout, 0u));
            } else {
                mbar_wait_cluster(bar_recvout, 0);
                sum += reinterpret_cast<const float*>(smem + OFF_RECVOUT)[tid];
                out[(tid >> 3) * D_ + pair * 8 + (tid & 7)] = __float2bfloat16_rn(sum);
            }
        }
        TL(11);
        if (tid == 0) {
            const unsigned int old = atomicAdd(&g_exitcnt, 1u);
            if (old == (unsigned)(NCTA - 1)) {
                g_epoch = tag;
                g_exitcnt = 0u;
            }
        }
    }
}

typedef CUresult (*PFN_tmapEncode)(CUtensorMap*, CUtensorMapDataType, cuuint32_t, void*, const cuuint64_t*,
                                   const cuuint64_t*, const cuuint32_t*, const cuuint32_t*, CUtensorMapInterleave,
                                   CUtensorMapSwizzle, CUtensorMapL2promotion, CUtensorMapFloatOOBfill);

void make_map(PFN_tmapEncode enc, CUtensorMap* m, const void* ptr, uint64_t cols, uint64_t rows, uint32_t boxc,
              uint32_t boxr, CUtensorMapSwizzle swz, CUtensorMapL2promotion prom) {
    cuuint64_t gdim[2] = {(cuuint64_t)cols, (cuuint64_t)rows};
    cuuint64_t gstr[1] = {(cuuint64_t)cols * 2};
    cuuint32_t box[2] = {boxc, boxr};
    cuuint32_t estr[2] = {1, 1};
    enc(m, CU_TENSOR_MAP_DATA_TYPE_BFLOAT16, 2, const_cast<void*>(ptr), gdim, gstr, box, estr,
        CU_TENSOR_MAP_INTERLEAVE_NONE, swz, prom, CU_TENSOR_MAP_FLOAT_OOB_FILL_NONE);
}

}

extern "C" void kernel_launch(void* const* d_in, const int* in_sizes, int n_in, void* d_out, int out_size) {
    const __nv_bfloat16* x = (const __nv_bfloat16*)d_in[0];
    const __nv_bfloat16* kc = (const __nv_bfloat16*)d_in[1];
    const __nv_bfloat16* vc = (const __nv_bfloat16*)d_in[2];
    const __nv_bfloat16* wq = (const __nv_bfloat16*)d_in[3];
    const __nv_bfloat16* wo = (const __nv_bfloat16*)d_in[4];
    __nv_bfloat16* out = (__nv_bfloat16*)d_out;

    static PFN_tmapEncode enc = nullptr;
    if (!enc) {
        void* fn = nullptr;
        cudaDriverEntryPointQueryResult qres;
        cudaGetDriverEntryPoint("cuTensorMapEncodeTiled", &fn, cudaEnableDefault, &qres);
        enc = (PFN_tmapEncode)fn;
        cudaFuncSetAttribute(fused_kernel, cudaFuncAttributeMaxDynamicSharedMemorySize, SMEM_BYTES);
    }
    CUtensorMap tmK, tmV, tmWq, tmWo;
    make_map(enc, &tmK, kc, DH_, (uint64_t)B_ * HKV_ * SK_, 64, KEYS_STAGE, CU_TENSOR_MAP_SWIZZLE_128B,
             CU_TENSOR_MAP_L2_PROMOTION_L2_256B);
    make_map(enc, &tmV, vc, DH_, (uint64_t)B_ * HKV_ * SK_, 64, KEYS_STAGE, CU_TENSOR_MAP_SWIZZLE_128B,
             CU_TENSOR_MAP_L2_PROMOTION_L2_256B);
    make_map(enc, &tmWq, wq, NQ_, D_, 32, 256, CU_TENSOR_MAP_SWIZZLE_64B, CU_TENSOR_MAP_L2_PROMOTION_NONE);
    make_map(enc, &tmWo, wo, D_, NQ_, 8, 256, CU_TENSOR_MAP_SWIZZLE_NONE, CU_TENSOR_MAP_L2_PROMOTION_NONE);

    fused_kernel<<<NCTA, NTHREADS, SMEM_BYTES>>>(tmK, tmV, tmWq, tmWo, x, out);
}
```
